```python
import torch

def _softmax(x, axis=-1):
    return torch.softmax(x, dim=axis)
def _gelu(x):
    return torch.nn.functional.gelu(x, approximate="tanh")
def _silu(x):
    return torch.nn.functional.silu(x)
def _sigmoid(x):
    return torch.sigmoid(x)
def _layernorm(x, axis=-1, eps=1e-5):
    m = x.mean(dim=axis, keepdim=True)
    v = x.var(dim=axis, keepdim=True, unbiased=False)
    return (x - m) / torch.sqrt(v + eps)
def _scatter_add(tgt, idx, src, axis=0):
    return tgt.clone().index_add_(axis, idx, src)
def _segment_sum(src, seg, n):
    out = torch.zeros((n,) + src.shape[1:], dtype=src.dtype)
    return out.index_add_(0, seg, src)
def _pad(x, pw):
    flat = tuple(v for pair in reversed(pw) for v in pair)
    return torch.nn.functional.pad(x, flat)

kernel_name = 'standalone__gqa_softmax__near_ridge'

def setup_inputs():

    _w = (lambda a: (lambda t: t.to(torch.bfloat16) if t.is_floating_point() else t)(torch.as_tensor(a)))
    B, Hq, Hkv, Sq, Sk, D = 8, 16, 8, 256, 512, 256
    return {
        "q": _w((lambda *s: torch.randn(*s, dtype=torch.bfloat16) * 0.8)(B, Hq, Sq, D)),
        "k": _w((lambda *s: torch.randn(*s, dtype=torch.bfloat16) * 0.8)(B, Hkv, Sk, D)),
        "v": _w((lambda *s: torch.randn(*s, dtype=torch.bfloat16) * 0.05)(B, Hkv, Sk, D)),
    }

def reference(q, k, v):
    B, Hq, Sq, D = q.shape
    Hkv = k.shape[1]
    rep = Hq // Hkv
    k = (lambda x, n, axis: torch.repeat_interleave(x, n, dim=axis))(k, rep, axis=1)
    v = (lambda x, n, axis: torch.repeat_interleave(x, n, dim=axis))(v, rep, axis=1)
    scale = D ** -0.5
    scores = torch.einsum("bhqd,bhkd->bhqk", q, k) * scale
    p = _softmax(scores, axis=-1)
    return torch.einsum("bhqk,bhkd->bhqd", p, v)
```

```cpp
#include <cuda_runtime.h>
#include <cuda_bf16.h>
#include <cuda.h>
#include <stdint.h>
#include <limits.h>

namespace {

constexpr int kD = 256;
constexpr int kSq = 256;
constexpr int kSk = 512;
constexpr int kQRows = 8 * 16 * kSq;
constexpr int kKvRows = 8 * 8 * kSk;
constexpr int kTiles = 2;
constexpr int kIters = kSk / 128;
constexpr int kCtas = 128;
constexpr int kThreads = 384;

constexpr uint32_t SM_Q = 0;
constexpr uint32_t SM_K = 65536;
constexpr uint32_t SM_V = 131072;
constexpr uint32_t SM_O = 196608;
constexpr uint32_t SM_BAR = 229376;
constexpr uint32_t SM_JUNK = SM_BAR + 256;
constexpr uint32_t kSmemBytes = SM_JUNK + 2048;

__host__ __device__ constexpr uint32_t FULL_Q(int w, int c) { return SM_BAR + (w * 4 + c) * 8; }
__host__ __device__ constexpr uint32_t FULL_K(int c) { return SM_BAR + 64 + c * 8; }
__host__ __device__ constexpr uint32_t FULL_V(int c) { return SM_BAR + 96 + c * 8; }
__host__ __device__ constexpr uint32_t EMPTY_K(int c) { return SM_BAR + 128 + c * 8; }
__host__ __device__ constexpr uint32_t EMPTY_V(int c) { return SM_BAR + 160 + c * 8; }
__host__ __device__ constexpr uint32_t EMPTY_Q(int w) { return SM_BAR + 192 + w * 8; }
constexpr uint32_t STAGE_FREE = SM_BAR + 208;
constexpr uint32_t ALL_LOADED = SM_BAR + 216;
constexpr uint32_t WARM_DONE = SM_BAR + 224;

constexpr int kNumBars = 29;
#define SUM_LEVELS 3
#define WARM_EVENTS 16
constexpr int kWarmEvents = WARM_EVENTS;
constexpr int kWarmStep = (32 * 16 + kWarmEvents - 1) / kWarmEvents;
#define WARM_FIRST 8
constexpr int kWarmFirst = WARM_FIRST;
#define PAIRING 1
#define PF_ITER 2
constexpr uint32_t kPfIter = PF_ITER;
constexpr int BAR_ORDER0 = 1;
constexpr int BAR_OREADY0 = 3;
constexpr int BAR_VDONE = 7;

__device__ __forceinline__ uint32_t smem_u32(const void* p) { return (uint32_t)__cvta_generic_to_shared(p); }

__device__ __forceinline__ void mbar_init(uint32_t bar, uint32_t count) {
    asm volatile("mbarrier.init.shared::cta.b64 [%0], %1;" ::"r"(bar), "r"(count) : "memory");
}
__device__ __forceinline__ void mbar_wait(uint32_t bar, uint32_t parity) {
    asm volatile(
        "{\n.reg .pred p;\n.reg .u32 n;\n"
        "mbarrier.try_wait.parity.shared::cta.b64 p, [%0], %1;\n"
        "@p bra WAIT_DONE;\n"
        "mov.u32 n, 0;\n"
        "WAIT_LOOP:\n"
        "mbarrier.try_wait.parity.shared::cta.b64 p, [%0], %1, 4000;\n"
        "@p bra WAIT_DONE;\n"
        "add.u32 n, n, 1;\n"
        "setp.lt.u32 p, n, 0x10000;\n"
        "@p bra WAIT_LOOP;\n"
        "trap;\n"
        "WAIT_DONE:\n}\n" ::"r"(bar), "r"(parity) : "memory");
}
__device__ __forceinline__ bool elect_one() {
    uint32_t ok;
    asm volatile("{\n.reg .pred p;\nelect.sync _|p, 0xffffffff;\nselp.b32 %0, 1, 0, p;\n}\n" : "=r"(ok));
    return ok != 0;
}
__device__ __forceinline__ void mbar_expect_tx(uint32_t bar, uint32_t bytes) {
    asm volatile("mbarrier.arrive.expect_tx.shared::cta.b64 _, [%0], %1;" ::"r"(bar), "r"(bytes) : "memory");
}
__device__ __forceinline__ void mbar_arrive(uint32_t bar) {
    asm volatile("mbarrier.arrive.shared::cta.b64 _, [%0];" ::"r"(bar) : "memory");
}
__device__ __forceinline__ void mbar_arrive_cluster(uint32_t cluster_addr) {
    asm volatile("mbarrier.arrive.shared::cluster.b64 _, [%0];" ::"r"(cluster_addr) : "memory");
}
__device__ __forceinline__ uint32_t mapa(uint32_t addr, uint32_t rank) {
    uint32_t r;
    asm("mapa.shared::cluster.u32 %0, %1, %2;" : "=r"(r) : "r"(addr), "r"(rank));
    return r;
}
__device__ __forceinline__ void tma_load_2d(uint32_t dst, const CUtensorMap* tm, uint32_t bar, int x, int y) {
    asm volatile(
        "cp.async.bulk.tensor.2d.shared::cluster.global.mbarrier::complete_tx::bytes [%0], [%1, {%3, %4}], [%2];"
        ::"r"(dst), "l"(tm), "r"(bar), "r"(x), "r"(y) : "memory");
}
__device__ __forceinline__ void tma_load_2d_mc(uint32_t dst, const CUtensorMap* tm, uint32_t bar, int x, int y) {
    asm volatile(
        "cp.async.bulk.tensor.2d.shared::cluster.global.mbarrier::complete_tx::bytes.multicast::cluster"
        " [%0], [%1, {%3, %4}], [%2], %5;"
        ::"r"(dst), "l"(tm), "r"(bar), "r"(x), "r"(y), "h"((uint16_t)3) : "memory");
}
__device__ __forceinline__ void tma_load_3d_mc(uint32_t dst, const CUtensorMap* tm, uint32_t bar, int x, int y, int z) {
    asm volatile(
        "cp.async.bulk.tensor.3d.shared::cluster.global.mbarrier::complete_tx::bytes.multicast::cluster"
        " [%0], [%1, {%3, %4, %5}], [%2], %6;"
        ::"r"(dst), "l"(tm), "r"(bar), "r"(x), "r"(y), "r"(z), "h"((uint16_t)3) : "memory");
}
__device__ __forceinline__ void tma_store_3d(const CUtensorMap* tm, uint32_t src, int x, int y, int z) {
    asm volatile("cp.async.bulk.tensor.3d.global.shared::cta.bulk_group [%0, {%2, %3, %4}], [%1];"
                 ::"l"(tm), "r"(src), "r"(x), "r"(y), "r"(z) : "memory");
}
__device__ __forceinline__ void l2_prefetch(const void* p, uint32_t bytes) {
    asm volatile("cp.async.bulk.prefetch.L2.global [%0], %1;" ::"l"(p), "r"(bytes) : "memory");
}
__device__ __forceinline__ void cluster_arrive_relaxed() { asm volatile("barrier.cluster.arrive.relaxed.aligned;" ::: "memory"); }
__device__ __forceinline__ void cluster_wait() { asm volatile("barrier.cluster.wait.acquire.aligned;" ::: "memory"); }
__device__ __forceinline__ void named_sync(int id, int n) { asm volatile("bar.sync %0, %1;" ::"r"(id), "r"(n) : "memory"); }
__device__ __forceinline__ void named_arrive(int id, int n) { asm volatile("bar.arrive %0, %1;" ::"r"(id), "r"(n) : "memory"); }
__device__ __forceinline__ void wg_fence() { asm volatile("wgmma.fence.sync.aligned;" ::: "memory"); }
__device__ __forceinline__ void wg_commit() { asm volatile("wgmma.commit_group.sync.aligned;" ::: "memory"); }
template <int N>
__device__ __forceinline__ void wg_wait() { asm volatile("wgmma.wait_group.sync.aligned %0;" ::"n"(N) : "memory"); }

__device__ __forceinline__ uint32_t desc_lo(uint32_t addr, uint32_t lbo_bytes) { return ((addr & 0x3FFFFu) >> 4) | ((lbo_bytes >> 4) << 16); }
__device__ __forceinline__ uint64_t desc_at(uint32_t lo, uint32_t byte_off) {
    constexpr uint32_t hi = (1024u >> 4) | (1u << 30);
    return ((uint64_t)hi << 32) | (lo + (byte_off >> 4));
}
__device__ __forceinline__ float ex2(float x) {
    float y;
    asm("ex2.approx.ftz.f32 %0, %1;" : "=f"(y) : "f"(x));
    return y;
}
__device__ __forceinline__ float rcp_approx(float x) {
    float y;
    asm("rcp.approx.ftz.f32 %0, %1;" : "=f"(y) : "f"(x));
    return y;
}
__device__ __forceinline__ uint32_t pack_bf16(float lo, float hi) {
    uint32_t r;
    asm("cvt.rn.bf16x2.f32 %0, %1, %2;" : "=r"(r) : "f"(hi), "f"(lo));
    return r;
}
__device__ __forceinline__ uint32_t add_bf16x2(uint32_t a, uint32_t b) {
    uint32_t r;
    asm("add.rn.bf16x2 %0, %1, %2;" : "=r"(r) : "r"(a), "r"(b));
    return r;
}
template <int N>
__device__ __forceinline__ void fence_regs(float (&d)[N]) {
#pragma unroll
    for (int i = 0; i < N; i++) asm volatile("" : "+f"(d[i])::"memory");
}

__device__ __forceinline__ void wgmma_qk_first(float (&d)[64], uint64_t da, uint64_t db) {
    asm volatile(
        "{\n.reg .pred p;\nsetp.ne.b32 p, 0, 0;\n"
        "wgmma.mma_async.sync.aligned.m64n128k16.f32.bf16.bf16 "
        "{%0, %1, %2, %3, %4, %5, %6, %7, %8, %9, %10, %11, %12, %13, %14, %15, "
        "%16, %17, %18, %19, %20, %21, %22, %23, %24, %25, %26, %27, %28, %29, %30, %31, "
        "%32, %33, %34, %35, %36, %37, %38, %39, %40, %41, %42, %43, %44, %45, %46, %47, "
        "%48, %49, %50, %51, %52, %53, %54, %55, %56, %57, %58, %59, %60, %61, %62, %63}, "
        "%64, %65, p, 1, 1, 0, 0;\n}\n"
        : "=f"(d[0]), "=f"(d[1]), "=f"(d[2]), "=f"(d[3]), "=f"(d[4]), "=f"(d[5]), "=f"(d[6]), "=f"(d[7]),
          "=f"(d[8]), "=f"(d[9]), "=f"(d[10]), "=f"(d[11]), "=f"(d[12]), "=f"(d[13]), "=f"(d[14]), "=f"(d[15]),
          "=f"(d[16]), "=f"(d[17]), "=f"(d[18]), "=f"(d[19]), "=f"(d[20]), "=f"(d[21]), "=f"(d[22]), "=f"(d[23]),
          "=f"(d[24]), "=f"(d[25]), "=f"(d[26]), "=f"(d[27]), "=f"(d[28]), "=f"(d[29]), "=f"(d[30]), "=f"(d[31]),
          "=f"(d[32]), "=f"(d[33]), "=f"(d[34]), "=f"(d[35]), "=f"(d[36]), "=f"(d[37]), "=f"(d[38]), "=f"(d[39]),
          "=f"(d[40]), "=f"(d[41]), "=f"(d[42]), "=f"(d[43]), "=f"(d[44]), "=f"(d[45]), "=f"(d[46]), "=f"(d[47]),
          "=f"(d[48]), "=f"(d[49]), "=f"(d[50]), "=f"(d[51]), "=f"(d[52]), "=f"(d[53]), "=f"(d[54]), "=f"(d[55]),
          "=f"(d[56]), "=f"(d[57]), "=f"(d[58]), "=f"(d[59]), "=f"(d[60]), "=f"(d[61]), "=f"(d[62]), "=f"(d[63])
        : "l"(da), "l"(db));
}

__device__ __forceinline__ void wgmma_qk(float (&d)[64], uint64_t da, uint64_t db) {
    asm volatile(
        "{\n.reg .pred p;\nsetp.ne.b32 p, 1, 0;\n"
        "wgmma.mma_async.sync.aligned.m64n128k16.f32.bf16.bf16 "
        "{%0, %1, %2, %3, %4, %5, %6, %7, %8, %9, %10, %11, %12, %13, %14, %15, "
        "%16, %17, %18, %19, %20, %21, %22, %23, %24, %25, %26, %27, %28, %29, %30, %31, "
        "%32, %33, %34, %35, %36, %37, %38, %39, %40, %41, %42, %43, %44, %45, %46, %47, "
        "%48, %49, %50, %51, %52, %53, %54, %55, %56, %57, %58, %59, %60, %61, %62, %63}, "
        "%64, %65, p, 1, 1, 0, 0;\n}\n"
        : "+f"(d[0]), "+f"(d[1]), "+f"(d[2]), "+f"(d[3]), "+f"(d[4]), "+f"(d[5]), "+f"(d[6]), "+f"(d[7]),
          "+f"(d[8]), "+f"(d[9]), "+f"(d[10]), "+f"(d[11]), "+f"(d[12]), "+f"(d[13]), "+f"(d[14]), "+f"(d[15]),
          "+f"(d[16]), "+f"(d[17]), "+f"(d[18]), "+f"(d[19]), "+f"(d[20]), "+f"(d[21]), "+f"(d[22]), "+f"(d[23]),
          "+f"(d[24]), "+f"(d[25]), "+f"(d[26]), "+f"(d[27]), "+f"(d[28]), "+f"(d[29]), "+f"(d[30]), "+f"(d[31]),
          "+f"(d[32]), "+f"(d[33]), "+f"(d[34]), "+f"(d[35]), "+f"(d[36]), "+f"(d[37]), "+f"(d[38]), "+f"(d[39]),
          "+f"(d[40]), "+f"(d[41]), "+f"(d[42]), "+f"(d[43]), "+f"(d[44]), "+f"(d[45]), "+f"(d[46]), "+f"(d[47]),
          "+f"(d[48]), "+f"(d[49]), "+f"(d[50]), "+f"(d[51]), "+f"(d[52]), "+f"(d[53]), "+f"(d[54]), "+f"(d[55]),
          "+f"(d[56]), "+f"(d[57]), "+f"(d[58]), "+f"(d[59]), "+f"(d[60]), "+f"(d[61]), "+f"(d[62]), "+f"(d[63])
        : "l"(da), "l"(db));
}

__device__ __forceinline__ void wgmma_pv(float (&d)[128], uint32_t a0, uint32_t a1, uint32_t a2, uint32_t a3,
                                              uint64_t db, int scale_d) {
    asm volatile(
        "{\n.reg .pred p;\nsetp.ne.b32 p, %133, 0;\n"
        "wgmma.mma_async.sync.aligned.m64n256k16.f32.bf16.bf16 "
        "{%0, %1, %2, %3, %4, %5, %6, %7, %8, %9, %10, %11, %12, %13, %14, %15, "
        "%16, %17, %18, %19, %20, %21, %22, %23, %24, %25, %26, %27, %28, %29, %30, %31, "
        "%32, %33, %34, %35, %36, %37, %38, %39, %40, %41, %42, %43, %44, %45, %46, %47, "
        "%48, %49, %50, %51, %52, %53, %54, %55, %56, %57, %58, %59, %60, %61, %62, %63, "
        "%64, %65, %66, %67, %68, %69, %70, %71, %72, %73, %74, %75, %76, %77, %78, %79, "
        "%80, %81, %82, %83, %84, %85, %86, %87, %88, %89, %90, %91, %92, %93, %94, %95, "
        "%96, %97, %98, %99, %100, %101, %102, %103, %104, %105, %106, %107, %108, %109, %110, %111, "
        "%112, %113, %114, %115, %116, %117, %118, %119, %120, %121, %122, %123, %124, %125, %126, %127}, "
        "{%128, %129, %130, %131}, %132, p, 1, 1, 1;\n}\n"
        : "+f"(d[0]), "+f"(d[1]), "+f"(d[2]), "+f"(d[3]), "+f"(d[4]), "+f"(d[5]), "+f"(d[6]), "+f"(d[7]),
          "+f"(d[8]), "+f"(d[9]), "+f"(d[10]), "+f"(d[11]), "+f"(d[12]), "+f"(d[13]), "+f"(d[14]), "+f"(d[15]),
          "+f"(d[16]), "+f"(d[17]), "+f"(d[18]), "+f"(d[19]), "+f"(d[20]), "+f"(d[21]), "+f"(d[22]), "+f"(d[23]),
          "+f"(d[24]), "+f"(d[25]), "+f"(d[26]), "+f"(d[27]), "+f"(d[28]), "+f"(d[29]), "+f"(d[30]), "+f"(d[31]),
          "+f"(d[32]), "+f"(d[33]), "+f"(d[34]), "+f"(d[35]), "+f"(d[36]), "+f"(d[37]), "+f"(d[38]), "+f"(d[39]),
          "+f"(d[40]), "+f"(d[41]), "+f"(d[42]), "+f"(d[43]), "+f"(d[44]), "+f"(d[45]), "+f"(d[46]), "+f"(d[47]),
          "+f"(d[48]), "+f"(d[49]), "+f"(d[50]), "+f"(d[51]), "+f"(d[52]), "+f"(d[53]), "+f"(d[54]), "+f"(d[55]),
          "+f"(d[56]), "+f"(d[57]), "+f"(d[58]), "+f"(d[59]), "+f"(d[60]), "+f"(d[61]), "+f"(d[62]), "+f"(d[63]),
          "+f"(d[64]), "+f"(d[65]), "+f"(d[66]), "+f"(d[67]), "+f"(d[68]), "+f"(d[69]), "+f"(d[70]), "+f"(d[71]),
          "+f"(d[72]), "+f"(d[73]), "+f"(d[74]), "+f"(d[75]), "+f"(d[76]), "+f"(d[77]), "+f"(d[78]), "+f"(d[79]),
          "+f"(d[80]), "+f"(d[81]), "+f"(d[82]), "+f"(d[83]), "+f"(d[84]), "+f"(d[85]), "+f"(d[86]), "+f"(d[87]),
          "+f"(d[88]), "+f"(d[89]), "+f"(d[90]), "+f"(d[91]), "+f"(d[92]), "+f"(d[93]), "+f"(d[94]), "+f"(d[95]),
          "+f"(d[96]), "+f"(d[97]), "+f"(d[98]), "+f"(d[99]), "+f"(d[100]), "+f"(d[101]), "+f"(d[102]), "+f"(d[103]),
          "+f"(d[104]), "+f"(d[105]), "+f"(d[106]), "+f"(d[107]), "+f"(d[108]), "+f"(d[109]), "+f"(d[110]), "+f"(d[111]),
          "+f"(d[112]), "+f"(d[113]), "+f"(d[114]), "+f"(d[115]), "+f"(d[116]), "+f"(d[117]), "+f"(d[118]), "+f"(d[119]),
          "+f"(d[120]), "+f"(d[121]), "+f"(d[122]), "+f"(d[123]), "+f"(d[124]), "+f"(d[125]), "+f"(d[126]), "+f"(d[127])
        : "r"(a0), "r"(a1), "r"(a2), "r"(a3), "l"(db), "r"(scale_d));
}

__global__ void __cluster_dims__(2, 1, 1) __launch_bounds__(kThreads, 1)
gqa_fwd_kernel(const __grid_constant__ CUtensorMap tmQ, const __grid_constant__ CUtensorMap tmK,
               const __grid_constant__ CUtensorMap tmV, const __grid_constant__ CUtensorMap tmO,
               const uint8_t* __restrict__ gq, const uint8_t* __restrict__ gk, const uint8_t* __restrict__ gv) {
    extern __shared__ __align__(1024) uint8_t smem_raw[];
    const uint32_t sb = smem_u32(smem_raw);
    const int wg = __shfl_sync(0xffffffffu, (int)(threadIdx.x >> 7), 0);
    const uint32_t rank = blockIdx.x & 1;
    int cl = blockIdx.x >> 1;
    if (cl >= 36) {
        const int i = cl - 36, round = i / 7, gpc = i - round * 7;
        cl = 2 * (18 + (round >> 1) * 7 + gpc) + (round & 1);
    } else if (cl >= 4) {
        const int i = cl - 4, round = i >> 3, gpc = i & 7;
        cl = 2 * (2 + (round >> 1) * 8 + gpc) + (round & 1);
    }

    const int warp_id = __shfl_sync(0xffffffffu, (int)(threadIdx.x >> 5), 0);
    if (warp_id == 8) {
        const bool one = elect_one();
        if (one) {
            asm volatile("prefetch.tensormap [%0];" ::"l"(&tmQ) : "memory");
            asm volatile("prefetch.tensormap [%0];" ::"l"(&tmK) : "memory");
            asm volatile("prefetch.tensormap [%0];" ::"l"(&tmV) : "memory");
#pragma unroll
            for (int i = 0; i < 8; i++) mbar_init(sb + SM_BAR + i * 8, 1);
            asm volatile("fence.mbarrier_init.release.cluster;" ::: "memory");
        }
        __syncwarp();
        cluster_arrive_relaxed();
        if (one) {
            const int g = cl >> 1;
            const int qrow = (2 * g + (cl & 1)) * kSq + (int)rank * 128;
            const size_t kv_off = ((size_t)g * kSk + ((cl & 1) * 2 + rank) * 32) * (kD * 2);
#pragma unroll
            for (int c = 0; c < 4; c++) {
                mbar_expect_tx(sb + FULL_Q(0, c), 8192);
                tma_load_2d(sb + SM_Q + c * 8192, &tmQ, sb + FULL_Q(0, c), c * 64, qrow);
            }
            l2_prefetch(gk + kv_off, 16384);
        }
        __syncwarp();
    } else if (warp_id == 9) {
        if (elect_one()) {
            asm volatile("prefetch.tensormap [%0];" ::"l"(&tmO) : "memory");
#pragma unroll
            for (int i = 8; i < kNumBars; i++) mbar_init(sb + SM_BAR + i * 8, ((i >= 16 && i < 24) || i == 27) ? 4 : 1);
            asm volatile("fence.mbarrier_init.release.cluster;" ::: "memory");
        }
        __syncwarp();
        cluster_arrive_relaxed();
    } else {
        cluster_arrive_relaxed();
    }
    cluster_wait();

    if (wg == 2) {
        asm volatile("setmaxnreg.dec.sync.aligned.u32 24;");
        if (warp_id == 8) {
            if (elect_one()) {
                uint32_t it = 0;
                for (int tile = 0; tile < kTiles; tile++) {
                    const int g = tile * 32 + (cl >> 1);
                    const int qrow = (2 * g + (cl & 1)) * kSq + (int)rank * 128;
                    for (int j = 0; j < kIters; j++, it++) {
                        const int krow = g * kSk + j * 128;
                        const uint32_t prev = (it - 1) & 1;
                        if (j == 0 && tile > 0) mbar_wait(sb + EMPTY_Q(0), 0);
#pragma unroll
                        for (int c = 0; c < 4; c++) {
                            if (j == 0 && tile > 0) {
                                mbar_expect_tx(sb + FULL_Q(0, c), 8192);
                                tma_load_2d(sb + SM_Q + c * 8192, &tmQ, sb + FULL_Q(0, c), c * 64, qrow);
                            }
                            if ((c & 1) == rank) {
                                if (it > 0) mbar_wait(sb + EMPTY_K(c), prev);
                                mbar_expect_tx(sb + FULL_K(c), 16384);
                                tma_load_2d_mc(sb + SM_K + c * 16384, &tmK, sb + FULL_K(c), c * 64, krow);
                            } else {
                                if (it > 0) mbar_wait(sb + FULL_K(c), prev);
                                mbar_expect_tx(sb + FULL_K(c), 16384);
                            }
                        }
                        if (j == 0) {
                            if (tile > 0) mbar_wait(sb + EMPTY_Q(1), 0);
#pragma unroll
                            for (int c = 0; c < 4; c++) {
                                mbar_expect_tx(sb + FULL_Q(1, c), 8192);
                                tma_load_2d(sb + SM_Q + 32768 + c * 8192, &tmQ, sb + FULL_Q(1, c), c * 64, qrow + 64);
                            }
                        }
#pragma unroll
                        for (int c = 0; c < 4; c++) {
                            if ((c & 1) == rank) {
                                if (it > 0) mbar_wait(sb + EMPTY_V(c), prev);
                                mbar_expect_tx(sb + FULL_V(c), 16384);
                                tma_load_3d_mc(sb + SM_V + c * 16384, &tmV, sb + FULL_V(c), 0, krow + c * 32, 0);
                            } else {
                                if (it > 0) mbar_wait(sb + FULL_V(c), prev);
                                mbar_expect_tx(sb + FULL_V(c), 16384);
                            }
                        }
                    }
                }
                mbar_wait(sb + ALL_LOADED, 0);
            }
        } else if (warp_id == 11) {
            if (elect_one()) {
                const uint8_t* src = gq + ((size_t)(2 * (32 + (cl >> 1)) + (cl & 1)) * kSq + rank * 128) * (kD * 2);
                mbar_expect_tx(sb + WARM_DONE, 65536);
#pragma unroll 1
                for (int c = 0; c < 8; c++) mbar_wait(sb + FULL_K(0) + c * 8, 0);
#pragma unroll 1
                for (int e = 0; e < kWarmEvents; e++) {
                    mbar_wait(sb + FULL_K(0) + ((e + kWarmFirst) & 7) * 8, ((e + kWarmFirst) >> 3) & 1);
                    const int p0 = (e * kWarmStep) >> 4, p1 = min(32, ((e + 1) * kWarmStep) >> 4);
                    for (int p = p0; p < p1; p++)
                        asm volatile("cp.async.bulk.shared::cluster.global.mbarrier::complete_tx::bytes [%0], [%1], 2048, [%2];"
                                     ::"r"(sb + SM_JUNK), "l"(src + p * 2048), "r"(sb + WARM_DONE) : "memory");
                }
                mbar_wait(sb + WARM_DONE, 0);
            }
        } else if (warp_id == 9) {
            const int qrow0 = (2 * (cl >> 1) + (cl & 1)) * kSq + (int)rank * 128;
            const int qrow1 = qrow0 + 64 * kSq;
#pragma unroll 1
            for (int h = 0; h < 2; h++) {
                named_sync(BAR_OREADY0 + 2 + h, 160);
                if (elect_one()) {
                    tma_store_3d(&tmO, sb + SM_V + 32768 + h * 16384, 0, qrow0 + 64, 2 * h);
                    asm volatile("cp.async.bulk.commit_group;" ::: "memory");
                    asm volatile("cp.async.bulk.wait_group.read 0;" ::: "memory");
                    mbar_arrive_cluster(mapa(sb, h) + EMPTY_V(2) + h * 8);
                }
                __syncwarp();
            }
#pragma unroll 1
            for (int h = 0; h < 2; h++) {
                named_sync(BAR_OREADY0 + h, 160);
                if (elect_one()) {
                    mbar_wait(sb + (h == 0 ? FULL_V(3) : FULL_K(3)), h);
                    tma_store_3d(&tmO, sb + SM_O + h * 16384, 0, qrow0, 2 * h);
                    asm volatile("cp.async.bulk.commit_group;" ::: "memory");
                    if (h == 1) {
                        asm volatile("cp.async.bulk.wait_group.read 0;" ::: "memory");
                        mbar_arrive(sb + STAGE_FREE);
                    }
                }
                __syncwarp();
            }
#pragma unroll 1
            for (int u = 0; u < 4; u++) {
                named_sync(BAR_OREADY0 + u, 160);
                if (elect_one()) {
                    const int w = u >> 1, h = u & 1;
                    tma_store_3d(&tmO, sb + (w == 0 ? SM_O : SM_V + 32768) + h * 16384, 0, qrow1 + w * 64, 2 * h);
                    asm volatile("cp.async.bulk.commit_group;" ::: "memory");
                    if (u == 3) {
                        asm volatile("cp.async.bulk.wait_group.read 0;" ::: "memory");
                    }
                }
                __syncwarp();
            }
        }
    } else {
        asm volatile("setmaxnreg.inc.sync.aligned.u32 240;");
        const int lane = threadIdx.x & 31;
        const int warp = (threadIdx.x >> 5) & 3;
        const bool leader = (threadIdx.x & 127) == 0;
        const uint32_t dq = desc_lo(sb + SM_Q + wg * 32768, 16);
        const uint32_t dk = desc_lo(sb + SM_K, 16);
        const uint32_t dv = desc_lo(sb + SM_V, 4096);
        const uint32_t peer0 = mapa(sb, 0), peer1 = mapa(sb, 1);
        const int my_order = BAR_ORDER0 + wg;
        constexpr float kScaleLog2e = 0.0625f * 1.4426950408889634f;
        constexpr float kRescaleLog2 = 8.0f;

        float o[128];
#pragma unroll
        for (int i = 0; i < 128; i++) o[i] = 0.f;

        if (wg == 1) named_arrive(BAR_ORDER0, 256);

        uint32_t it = 0;
#pragma unroll 1
        for (int tile = 0; tile < kTiles; tile++) {
            float m0 = -INFINITY, m1 = -INFINITY, l0 = 0.f, l1 = 0.f;
            int thr0 = INT_MIN, thr1 = INT_MIN;
#pragma unroll 1
            for (int j = 0; j < kIters; j++, it++) {
                const uint32_t par = it & 1;
                const bool release = leader && (it != kTiles * kIters - 1);
                float s[64];
                named_sync(my_order, 256);
#pragma unroll
                for (int c = 0; c < 4; c++) {
                    if (j == 0) mbar_wait(sb + FULL_Q(0, c) + wg * 32, tile & 1);
                    mbar_wait(sb + FULL_K(c), par);
                    if (c == 0) wg_fence();
#pragma unroll
                    for (int kk = 0; kk < 4; kk++) {
                        const uint64_t da = desc_at(dq, c * 8192 + kk * 32);
                        const uint64_t db = desc_at(dk, c * 16384 + kk * 32);
                        if (c == 0 && kk == 0) wgmma_qk_first(s, da, db);
                        else wgmma_qk(s, da, db);
                    }
                    wg_commit();
                }
                if (wg == 0) named_arrive(BAR_ORDER0 + 1, 256);
                wg_wait<3>();
                if (release) mbar_arrive_cluster(peer0 + EMPTY_K(0));
                wg_wait<2>();
                if (release) mbar_arrive_cluster(peer1 + EMPTY_K(1));
                wg_wait<1>();
                if (release) mbar_arrive_cluster(peer0 + EMPTY_K(2));
                wg_wait<0>();
                fence_regs(s);
                if (release) mbar_arrive_cluster(peer1 + EMPTY_K(3));
                if (leader && j == kIters - 1 && tile == 0) mbar_arrive(sb + EMPTY_Q(0) + wg * 8);

                int ia[3], ib[3];
#pragma unroll
                for (int q = 0; q < 3; q++) {
                    const int i0 = q * 5;
                    ia[q] = __vimax3_s32(__float_as_int(s[4 * i0]), __float_as_int(s[4 * i0 + 1]), __float_as_int(s[4 * i0 + 4]));
                    ib[q] = __vimax3_s32(__float_as_int(s[4 * i0 + 2]), __float_as_int(s[4 * i0 + 3]), __float_as_int(s[4 * i0 + 6]));
                    ia[q] = __vimax3_s32(ia[q], __float_as_int(s[4 * i0 + 5]), __float_as_int(s[4 * i0 + 8]));
                    ib[q] = __vimax3_s32(ib[q], __float_as_int(s[4 * i0 + 7]), __float_as_int(s[4 * i0 + 10]));
                    ia[q] = __vimax3_s32(ia[q], __float_as_int(s[4 * i0 + 9]), __float_as_int(s[4 * i0 + 12]));
                    ib[q] = __vimax3_s32(ib[q], __float_as_int(s[4 * i0 + 11]), __float_as_int(s[4 * i0 + 14]));
                    ia[q] = __vimax3_s32(ia[q], __float_as_int(s[4 * i0 + 13]), __float_as_int(s[4 * i0 + 16]));
                    ib[q] = __vimax3_s32(ib[q], __float_as_int(s[4 * i0 + 15]), __float_as_int(s[4 * i0 + 18]));
                    ia[q] = max(ia[q], __float_as_int(s[4 * i0 + 17]));
                    ib[q] = max(ib[q], __float_as_int(s[4 * i0 + 19]));
                }
                int im0 = __vimax3_s32(ia[0], ia[1], ia[2]), im1 = __vimax3_s32(ib[0], ib[1], ib[2]);
                im0 = __vimax3_s32(im0, __float_as_int(s[60]), __float_as_int(s[61]));
                im1 = __vimax3_s32(im1, __float_as_int(s[62]), __float_as_int(s[63]));
                if (__any_sync(0xffffffffu, im0 >= thr0 || im1 >= thr1)) {
                    im0 = max(im0, __shfl_xor_sync(0xffffffffu, im0, 1));
                    im1 = max(im1, __shfl_xor_sync(0xffffffffu, im1, 1));
                    im0 = max(im0, __shfl_xor_sync(0xffffffffu, im0, 2));
                    im1 = max(im1, __shfl_xor_sync(0xffffffffu, im1, 2));
                    float mx0 = __int_as_float(im0), mx1 = __int_as_float(im1);
                    if (__any_sync(0xffffffffu, (im0 | im1) < 0)) {
                        mx0 = fmaxf(s[0], s[1]);
                        mx1 = fmaxf(s[2], s[3]);
#pragma unroll
                        for (int i = 1; i < 16; i++) {
                            mx0 = fmaxf(mx0, fmaxf(s[4 * i], s[4 * i + 1]));
                            mx1 = fmaxf(mx1, fmaxf(s[4 * i + 2], s[4 * i + 3]));
                        }
                        mx0 = fmaxf(mx0, __shfl_xor_sync(0xffffffffu, mx0, 1));
                        mx1 = fmaxf(mx1, __shfl_xor_sync(0xffffffffu, mx1, 1));
                        mx0 = fmaxf(mx0, __shfl_xor_sync(0xffffffffu, mx0, 2));
                        mx1 = fmaxf(mx1, __shfl_xor_sync(0xffffffffu, mx1, 2));
                    }
                    const float mn0 = fmaxf(m0, mx0 * kScaleLog2e), mn1 = fmaxf(m1, mx1 * kScaleLog2e);
                    const float al0 = ex2(m0 - mn0), al1 = ex2(m1 - mn1);
                    m0 = mn0;
                    m1 = mn1;
                    const float lim0 = (mn0 + kRescaleLog2) * (1.0f / kScaleLog2e), lim1 = (mn1 + kRescaleLog2) * (1.0f / kScaleLog2e);
                    thr0 = lim0 >= 0.f ? __float_as_int(lim0) : INT_MIN;
                    thr1 = lim1 >= 0.f ? __float_as_int(lim1) : INT_MIN;
                    l0 *= al0;
                    l1 *= al1;
                    if (j > 0) {
#pragma unroll
                        for (int i = 0; i < 128; i++) o[i] *= (i & 2) ? al1 : al0;
                    }
                }
                uint32_t p[32];
                auto exp_chunk = [&](int c) {
#pragma unroll
                    for (int kk = 2 * c; kk < 2 * c + 2; kk++) {
                        float e[8];
#pragma unroll
                        for (int i = 0; i < 8; i++) e[i] = ex2(fmaf(s[8 * kk + i], kScaleLog2e, (i & 2) ? -m1 : -m0));
                        p[4 * kk + 0] = pack_bf16(e[0], e[1]);
                        p[4 * kk + 1] = pack_bf16(e[2], e[3]);
                        p[4 * kk + 2] = pack_bf16(e[4], e[5]);
                        p[4 * kk + 3] = pack_bf16(e[6], e[7]);
                    }
                };
                exp_chunk(0);
#pragma unroll
                for (int c = 0; c < 4; c++) {
                    if (c < 3) exp_chunk(c + 1);
                    mbar_wait(sb + FULL_V(c), par);
                    wg_fence();
#pragma unroll
                    for (int kk = 0; kk < 2; kk++) {
                        const int k8 = c * 2 + kk;
                        const uint64_t db = desc_at(dv, c * 16384 + kk * 2048);
                        wgmma_pv(o, p[4 * k8], p[4 * k8 + 1], p[4 * k8 + 2], p[4 * k8 + 3], db, (k8 == 0) ? j : 1);
                    }
                    wg_commit();
                }
                if (it != kTiles * kIters - 1) {
                    if (wg == 1) named_arrive(BAR_ORDER0, 256);
                } else if (leader) {
                    mbar_arrive_cluster(peer0 + ALL_LOADED);
                    mbar_arrive_cluster(peer1 + ALL_LOADED);
                }
                wg_wait<3>();
                if (release) mbar_arrive_cluster(peer0 + EMPTY_V(0));
                wg_wait<2>();
                if (release) mbar_arrive_cluster(peer1 + EMPTY_V(1));
                const bool release_hi = release && !(wg == 1 && j == kIters - 1);
                wg_wait<1>();
                if (release_hi) mbar_arrive_cluster(peer0 + EMPTY_V(2));
                wg_wait<0>();
                fence_regs(o);
                if (release_hi) mbar_arrive_cluster(peer1 + EMPTY_V(3));
                if (wg == 0 && j == kIters - 1) named_arrive(BAR_VDONE, 256);

                {
                    uint32_t u0[8], u1[8];
#pragma unroll
                    for (int i = 0; i < 8; i++) {
                        u0[i] = add_bf16x2(p[4 * i], p[4 * i + 2]);
                        u1[i] = add_bf16x2(p[4 * i + 1], p[4 * i + 3]);
                    }
#pragma unroll
                    for (int i = 0; i < 4; i++) {
                        u0[i] = add_bf16x2(u0[i], u0[i + 4]);
                        u1[i] = add_bf16x2(u1[i], u1[i + 4]);
                    }
#pragma unroll
                    for (int i = 0; i < 2; i++) {
                        u0[i] = add_bf16x2(u0[i], u0[i + 2]);
                        u1[i] = add_bf16x2(u1[i], u1[i + 2]);
                    }
                    constexpr int kLeft = 16 >> SUM_LEVELS;
                    float a0 = 0.f, a1 = 0.f, b0 = 0.f, b1 = 0.f;
#pragma unroll
                    for (int i = 0; i < kLeft; i++) {
                        a0 += __uint_as_float(u0[i] << 16);
                        b0 += __uint_as_float(u0[i] & 0xffff0000u);
                        a1 += __uint_as_float(u1[i] << 16);
                        b1 += __uint_as_float(u1[i] & 0xffff0000u);
                    }
                    l0 += a0 + b0;
                    l1 += a1 + b1;
                }
            }

            l0 += __shfl_xor_sync(0xffffffffu, l0, 1);
            l1 += __shfl_xor_sync(0xffffffffu, l1, 1);
            l0 += __shfl_xor_sync(0xffffffffu, l0, 2);
            l1 += __shfl_xor_sync(0xffffffffu, l1, 2);
            const float inv0 = rcp_approx(l0), inv1 = rcp_approx(l1);
            const int r = lane & 7, mi = lane >> 3;
            const uint32_t row = warp * 16 + r + 8 * (mi & 1);
            const uint32_t stage = sb + (wg == 0 ? SM_O : SM_V + 32768);
            const uint32_t st_base = stage + row * 128 + (((mi >> 1) ^ r) << 4);
            if (wg == 0) {
                if (tile > 0) mbar_wait(sb + STAGE_FREE, 0);
            } else {
                named_sync(BAR_VDONE, 256);
            }
#pragma unroll
            for (int i = 0; i < 16; i++) {
                const uint32_t r0 = pack_bf16(o[8 * i + 0] * inv0, o[8 * i + 1] * inv0);
                const uint32_t r1 = pack_bf16(o[8 * i + 2] * inv1, o[8 * i + 3] * inv1);
                const uint32_t r2 = pack_bf16(o[8 * i + 4] * inv0, o[8 * i + 5] * inv0);
                const uint32_t r3 = pack_bf16(o[8 * i + 6] * inv1, o[8 * i + 7] * inv1);
                const uint32_t addr = (st_base ^ ((i & 3) << 5)) + (i >> 2) * 8192;
                asm volatile("stmatrix.sync.aligned.m8n8.x4.shared.b16 [%0], {%1, %2, %3, %4};"
                             ::"r"(addr), "r"(r0), "r"(r1), "r"(r2), "r"(r3) : "memory");
                if (i == 7 || i == 15) {
                    asm volatile("fence.proxy.async.shared::cta;" ::: "memory");
                    named_arrive(BAR_OREADY0 + wg * 2 + (i >> 3), 160);
                }
            }
        }
    }
}

typedef CUresult (*EncodeTiledFn)(CUtensorMap*, CUtensorMapDataType, cuuint32_t, void*, const cuuint64_t*,
                                  const cuuint64_t*, const cuuint32_t*, const cuuint32_t*, CUtensorMapInterleave,
                                  CUtensorMapSwizzle, CUtensorMapL2promotion, CUtensorMapFloatOOBfill);

void encode_2d(EncodeTiledFn fn, CUtensorMap* m, void* ptr, uint64_t rows, uint32_t box_rows) {
    cuuint64_t dims[2] = {(cuuint64_t)kD, rows};
    cuuint64_t strides[1] = {(cuuint64_t)kD * 2};
    cuuint32_t box[2] = {64, box_rows};
    cuuint32_t es[2] = {1, 1};
    fn(m, CU_TENSOR_MAP_DATA_TYPE_BFLOAT16, 2, ptr, dims, strides, box, es, CU_TENSOR_MAP_INTERLEAVE_NONE,
       CU_TENSOR_MAP_SWIZZLE_128B, CU_TENSOR_MAP_L2_PROMOTION_L2_128B, CU_TENSOR_MAP_FLOAT_OOB_FILL_NONE);
}
void encode_3d(EncodeTiledFn fn, CUtensorMap* m, void* ptr, uint64_t rows, uint32_t box_rows, uint32_t box_blocks) {
    cuuint64_t dims[3] = {64, rows, 4};
    cuuint64_t strides[2] = {(cuuint64_t)kD * 2, 128};
    cuuint32_t box[3] = {64, box_rows, box_blocks};
    cuuint32_t es[3] = {1, 1, 1};
    fn(m, CU_TENSOR_MAP_DATA_TYPE_BFLOAT16, 3, ptr, dims, strides, box, es, CU_TENSOR_MAP_INTERLEAVE_NONE,
       CU_TENSOR_MAP_SWIZZLE_128B, CU_TENSOR_MAP_L2_PROMOTION_L2_128B, CU_TENSOR_MAP_FLOAT_OOB_FILL_NONE);
}

}

extern "C" void kernel_launch(void* const* d_in, const int* in_sizes, int n_in, void* d_out, int out_size) {
    static EncodeTiledFn encode = nullptr;
    if (!encode) {
        void* fn = nullptr;
        cudaDriverEntryPointQueryResult qr;
        cudaGetDriverEntryPoint("cuTensorMapEncodeTiled", &fn, cudaEnableDefault, &qr);
        encode = (EncodeTiledFn)fn;
        cudaFuncSetAttribute(gqa_fwd_kernel, cudaFuncAttributeMaxDynamicSharedMemorySize, kSmemBytes);
    }
    CUtensorMap tmQ, tmK, tmV, tmO;
    encode_2d(encode, &tmQ, d_in[0], kQRows, 64);
    encode_2d(encode, &tmK, d_in[1], kKvRows, 128);
    encode_3d(encode, &tmV, d_in[2], kKvRows, 32, 4);
    encode_3d(encode, &tmO, d_out, kQRows, 64, 2);
    gqa_fwd_kernel<<<kCtas, kThreads, kSmemBytes>>>(tmQ, tmK, tmV, tmO, (const uint8_t*)d_in[0], (const uint8_t*)d_in[1],
                                                    (const uint8_t*)d_in[2]);
}
```

```cpp
#include <cuda_runtime.h>
#include <cuda_bf16.h>
#include <cuda.h>
#include <stdint.h>
#include <limits.h>

namespace {

constexpr int kD = 256;
constexpr int kSq = 256;
constexpr int kSk = 512;
constexpr int kQRows = 8 * 16 * kSq;
constexpr int kKvRows = 8 * 8 * kSk;
constexpr int kTiles = 2;
constexpr int kIters = kSk / 128;
constexpr int kCtas = 128;
constexpr int kThreads = 384;

constexpr uint32_t SM_Q = 0;
constexpr uint32_t SM_K = 65536;
constexpr uint32_t SM_V = 131072;
constexpr uint32_t SM_O = 196608;
constexpr uint32_t SM_BAR = 229376;
constexpr uint32_t SM_JUNK = SM_BAR + 256;
constexpr uint32_t kSmemBytes = SM_JUNK + 2048;

__host__ __device__ constexpr uint32_t FULL_Q(int w, int c) { return SM_BAR + (w * 4 + c) * 8; }
__host__ __device__ constexpr uint32_t FULL_K(int c) { return SM_BAR + 64 + c * 8; }
__host__ __device__ constexpr uint32_t FULL_V(int c) { return SM_BAR + 96 + c * 8; }
__host__ __device__ constexpr uint32_t EMPTY_K(int c) { return SM_BAR + 128 + c * 8; }
__host__ __device__ constexpr uint32_t EMPTY_V(int c) { return SM_BAR + 160 + c * 8; }
__host__ __device__ constexpr uint32_t EMPTY_Q(int w) { return SM_BAR + 192 + w * 8; }
constexpr uint32_t ALL_LOADED = SM_BAR + 208;
constexpr uint32_t WARM_DONE = SM_BAR + 216;
constexpr int kNumBars = 28;
__host__ __device__ constexpr uint32_t bar_count(int i) { return ((i >= 16 && i < 24) || i == 26) ? 4 : 1; }

constexpr int BAR_FIRST_PV = 0;
constexpr int BAR_ORDER0 = 1;
constexpr int BAR_OREADY0 = 3;
constexpr int BAR_VDONE = 7;
constexpr int BAR_OLAST0 = 8;

constexpr uint32_t kStagger = 800;
constexpr int kWarmFirst = 10;
constexpr int kWarmEvents = 20;
constexpr int kWarmStep = (32 * 16 + kWarmEvents - 1) / kWarmEvents;

__device__ __forceinline__ uint32_t smem_u32(const void* p) { return (uint32_t)__cvta_generic_to_shared(p); }

__device__ __forceinline__ void mbar_init(uint32_t bar, uint32_t count) {
    asm volatile("mbarrier.init.shared::cta.b64 [%0], %1;" ::"r"(bar), "r"(count) : "memory");
}
__device__ __forceinline__ void mbar_wait(uint32_t bar, uint32_t parity) {
    asm volatile(
        "{\n.reg .pred p;\n.reg .u32 n;\n"
        "mbarrier.try_wait.parity.shared::cta.b64 p, [%0], %1;\n"
        "@p bra WAIT_DONE;\n"
        "mov.u32 n, 0;\n"
        "WAIT_LOOP:\n"
        "mbarrier.try_wait.parity.shared::cta.b64 p, [%0], %1, 4000;\n"
        "@p bra WAIT_DONE;\n"
        "add.u32 n, n, 1;\n"
        "setp.lt.u32 p, n, 0x400000;\n"
        "@p bra WAIT_LOOP;\n"
        "trap;\n"
        "WAIT_DONE:\n}\n" ::"r"(bar), "r"(parity) : "memory");
}
template <int V>
struct IntC {
    static constexpr int value = V;
};
__device__ __forceinline__ bool elect_one() {
    uint32_t ok;
    asm volatile("{\n.reg .pred p;\nelect.sync _|p, 0xffffffff;\nselp.b32 %0, 1, 0, p;\n}\n" : "=r"(ok));
    return ok != 0;
}
__device__ __forceinline__ void mbar_expect_tx(uint32_t bar, uint32_t bytes) {
    asm volatile("mbarrier.arrive.expect_tx.shared::cta.b64 _, [%0], %1;" ::"r"(bar), "r"(bytes) : "memory");
}
__device__ __forceinline__ void mbar_arrive(uint32_t bar) {
    asm volatile("mbarrier.arrive.shared::cta.b64 _, [%0];" ::"r"(bar) : "memory");
}
__device__ __forceinline__ void mbar_arrive_cluster(uint32_t cluster_addr) {
    asm volatile("mbarrier.arrive.shared::cluster.b64 _, [%0];" ::"r"(cluster_addr) : "memory");
}
__device__ __forceinline__ uint32_t mapa(uint32_t addr, uint32_t rank) {
    uint32_t r;
    asm("mapa.shared::cluster.u32 %0, %1, %2;" : "=r"(r) : "r"(addr), "r"(rank));
    return r;
}
__device__ __forceinline__ void tma_load_2d(uint32_t dst, const CUtensorMap* tm, uint32_t bar, int x, int y) {
    asm volatile(
        "cp.async.bulk.tensor.2d.shared::cluster.global.mbarrier::complete_tx::bytes [%0], [%1, {%3, %4}], [%2];"
        ::"r"(dst), "l"(tm), "r"(bar), "r"(x), "r"(y) : "memory");
}
__device__ __forceinline__ void tma_load_2d_mc(uint32_t dst, const CUtensorMap* tm, uint32_t bar, int x, int y) {
    asm volatile(
        "cp.async.bulk.tensor.2d.shared::cluster.global.mbarrier::complete_tx::bytes.multicast::cluster"
        " [%0], [%1, {%3, %4}], [%2], %5;"
        ::"r"(dst), "l"(tm), "r"(bar), "r"(x), "r"(y), "h"((uint16_t)3) : "memory");
}
__device__ __forceinline__ void tma_load_3d_mc(uint32_t dst, const CUtensorMap* tm, uint32_t bar, int x, int y, int z) {
    asm volatile(
        "cp.async.bulk.tensor.3d.shared::cluster.global.mbarrier::complete_tx::bytes.multicast::cluster"
        " [%0], [%1, {%3, %4, %5}], [%2], %6;"
        ::"r"(dst), "l"(tm), "r"(bar), "r"(x), "r"(y), "r"(z), "h"((uint16_t)3) : "memory");
}
__device__ __forceinline__ void tma_store_3d(const CUtensorMap* tm, uint32_t src, int x, int y, int z) {
    asm volatile("cp.async.bulk.tensor.3d.global.shared::cta.bulk_group [%0, {%2, %3, %4}], [%1];"
                 ::"l"(tm), "r"(src), "r"(x), "r"(y), "r"(z) : "memory");
}
__device__ __forceinline__ void l2_prefetch(const void* p, uint32_t bytes) {
    asm volatile("cp.async.bulk.prefetch.L2.global [%0], %1;" ::"l"(p), "r"(bytes) : "memory");
}
__device__ __forceinline__ void cluster_arrive_relaxed() { asm volatile("barrier.cluster.arrive.relaxed.aligned;" ::: "memory"); }
__device__ __forceinline__ void cluster_wait() { asm volatile("barrier.cluster.wait.acquire.aligned;" ::: "memory"); }
__device__ __forceinline__ void named_sync(int id, int n) { asm volatile("bar.sync %0, %1;" ::"r"(id), "r"(n) : "memory"); }
__device__ __forceinline__ void named_arrive(int id, int n) { asm volatile("bar.arrive %0, %1;" ::"r"(id), "r"(n) : "memory"); }
__device__ __forceinline__ void wg_fence() { asm volatile("wgmma.fence.sync.aligned;" ::: "memory"); }
__device__ __forceinline__ void wg_commit() { asm volatile("wgmma.commit_group.sync.aligned;" ::: "memory"); }
template <int N>
__device__ __forceinline__ void wg_wait() { asm volatile("wgmma.wait_group.sync.aligned %0;" ::"n"(N) : "memory"); }

__device__ __forceinline__ uint32_t desc_lo(uint32_t addr, uint32_t lbo_bytes) { return ((addr & 0x3FFFFu) >> 4) | ((lbo_bytes >> 4) << 16); }
__device__ __forceinline__ uint64_t desc_at(uint32_t lo, uint32_t byte_off) {
    constexpr uint32_t hi = (1024u >> 4) | (1u << 30);
    return ((uint64_t)hi << 32) | (lo + (byte_off >> 4));
}
__device__ __forceinline__ float ex2(float x) {
    float y;
    asm("ex2.approx.ftz.f32 %0, %1;" : "=f"(y) : "f"(x));
    return y;
}
__device__ __forceinline__ float rcp_approx(float x) {
    float y;
    asm("rcp.approx.ftz.f32 %0, %1;" : "=f"(y) : "f"(x));
    return y;
}
__device__ __forceinline__ uint32_t pack_bf16(float lo, float hi) {
    uint32_t r;
    asm("cvt.rn.bf16x2.f32 %0, %1, %2;" : "=r"(r) : "f"(hi), "f"(lo));
    return r;
}
template <int N>
__device__ __forceinline__ void fence_regs(float (&d)[N]) {
#pragma unroll
    for (int i = 0; i < N; i++) asm volatile("" : "+f"(d[i])::"memory");
}

template <int OFF>
__device__ __forceinline__ void fence_regs_range(float (&d)[128]) {
#pragma unroll
    for (int i = OFF; i < OFF + 64; i++) asm volatile("" : "+f"(d[i])::"memory");
}

__device__ __forceinline__ void wgmma_qk_first(float (&d)[64], uint64_t da, uint64_t db) {
    asm volatile(
        "{\n.reg .pred p;\nsetp.ne.b32 p, 0, 0;\n"
        "wgmma.mma_async.sync.aligned.m64n128k16.f32.bf16.bf16 "
        "{%0, %1, %2, %3, %4, %5, %6, %7, %8, %9, %10, %11, %12, %13, %14, %15, "
        "%16, %17, %18, %19, %20, %21, %22, %23, %24, %25, %26, %27, %28, %29, %30, %31, "
        "%32, %33, %34, %35, %36, %37, %38, %39, %40, %41, %42, %43, %44, %45, %46, %47, "
        "%48, %49, %50, %51, %52, %53, %54, %55, %56, %57, %58, %59, %60, %61, %62, %63}, "
        "%64, %65, p, 1, 1, 0, 0;\n}\n"
        : "=f"(d[0]), "=f"(d[1]), "=f"(d[2]), "=f"(d[3]), "=f"(d[4]), "=f"(d[5]), "=f"(d[6]), "=f"(d[7]),
          "=f"(d[8]), "=f"(d[9]), "=f"(d[10]), "=f"(d[11]), "=f"(d[12]), "=f"(d[13]), "=f"(d[14]), "=f"(d[15]),
          "=f"(d[16]), "=f"(d[17]), "=f"(d[18]), "=f"(d[19]), "=f"(d[20]), "=f"(d[21]), "=f"(d[22]), "=f"(d[23]),
          "=f"(d[24]), "=f"(d[25]), "=f"(d[26]), "=f"(d[27]), "=f"(d[28]), "=f"(d[29]), "=f"(d[30]), "=f"(d[31]),
          "=f"(d[32]), "=f"(d[33]), "=f"(d[34]), "=f"(d[35]), "=f"(d[36]), "=f"(d[37]), "=f"(d[38]), "=f"(d[39]),
          "=f"(d[40]), "=f"(d[41]), "=f"(d[42]), "=f"(d[43]), "=f"(d[44]), "=f"(d[45]), "=f"(d[46]), "=f"(d[47]),
          "=f"(d[48]), "=f"(d[49]), "=f"(d[50]), "=f"(d[51]), "=f"(d[52]), "=f"(d[53]), "=f"(d[54]), "=f"(d[55]),
          "=f"(d[56]), "=f"(d[57]), "=f"(d[58]), "=f"(d[59]), "=f"(d[60]), "=f"(d[61]), "=f"(d[62]), "=f"(d[63])
        : "l"(da), "l"(db));
}

__device__ __forceinline__ void wgmma_qk(float (&d)[64], uint64_t da, uint64_t db) {
    asm volatile(
        "{\n.reg .pred p;\nsetp.ne.b32 p, 1, 0;\n"
        "wgmma.mma_async.sync.aligned.m64n128k16.f32.bf16.bf16 "
        "{%0, %1, %2, %3, %4, %5, %6, %7, %8, %9, %10, %11, %12, %13, %14, %15, "
        "%16, %17, %18, %19, %20, %21, %22, %23, %24, %25, %26, %27, %28, %29, %30, %31, "
        "%32, %33, %34, %35, %36, %37, %38, %39, %40, %41, %42, %43, %44, %45, %46, %47, "
        "%48, %49, %50, %51, %52, %53, %54, %55, %56, %57, %58, %59, %60, %61, %62, %63}, "
        "%64, %65, p, 1, 1, 0, 0;\n}\n"
        : "+f"(d[0]), "+f"(d[1]), "+f"(d[2]), "+f"(d[3]), "+f"(d[4]), "+f"(d[5]), "+f"(d[6]), "+f"(d[7]),
          "+f"(d[8]), "+f"(d[9]), "+f"(d[10]), "+f"(d[11]), "+f"(d[12]), "+f"(d[13]), "+f"(d[14]), "+f"(d[15]),
          "+f"(d[16]), "+f"(d[17]), "+f"(d[18]), "+f"(d[19]), "+f"(d[20]), "+f"(d[21]), "+f"(d[22]), "+f"(d[23]),
          "+f"(d[24]), "+f"(d[25]), "+f"(d[26]), "+f"(d[27]), "+f"(d[28]), "+f"(d[29]), "+f"(d[30]), "+f"(d[31]),
          "+f"(d[32]), "+f"(d[33]), "+f"(d[34]), "+f"(d[35]), "+f"(d[36]), "+f"(d[37]), "+f"(d[38]), "+f"(d[39]),
          "+f"(d[40]), "+f"(d[41]), "+f"(d[42]), "+f"(d[43]), "+f"(d[44]), "+f"(d[45]), "+f"(d[46]), "+f"(d[47]),
          "+f"(d[48]), "+f"(d[49]), "+f"(d[50]), "+f"(d[51]), "+f"(d[52]), "+f"(d[53]), "+f"(d[54]), "+f"(d[55]),
          "+f"(d[56]), "+f"(d[57]), "+f"(d[58]), "+f"(d[59]), "+f"(d[60]), "+f"(d[61]), "+f"(d[62]), "+f"(d[63])
        : "l"(da), "l"(db));
}

template <int OFF>
__device__ __forceinline__ void wgmma_pv_half(float (&d)[128], uint32_t a0, uint32_t a1, uint32_t a2, uint32_t a3, uint64_t db, int scale_d) {
    asm volatile(
        "{\n.reg .pred p;\nsetp.ne.b32 p, %69, 0;\n"
        "wgmma.mma_async.sync.aligned.m64n128k16.f32.bf16.bf16 "
        "{%0, %1, %2, %3, %4, %5, %6, %7, %8, %9, %10, %11, %12, %13, %14, %15, "
        "%16, %17, %18, %19, %20, %21, %22, %23, %24, %25, %26, %27, %28, %29, %30, %31, "
        "%32, %33, %34, %35, %36, %37, %38, %39, %40, %41, %42, %43, %44, %45, %46, %47, "
        "%48, %49, %50, %51, %52, %53, %54, %55, %56, %57, %58, %59, %60, %61, %62, %63}, "
        "{%64, %65, %66, %67}, %68, p, 1, 1, 1;\n}\n"
        : "+f"(d[OFF + 0]), "+f"(d[OFF + 1]), "+f"(d[OFF + 2]), "+f"(d[OFF + 3]), "+f"(d[OFF + 4]), "+f"(d[OFF + 5]), "+f"(d[OFF + 6]), "+f"(d[OFF + 7]),
          "+f"(d[OFF + 8]), "+f"(d[OFF + 9]), "+f"(d[OFF + 10]), "+f"(d[OFF + 11]), "+f"(d[OFF + 12]), "+f"(d[OFF + 13]), "+f"(d[OFF + 14]), "+f"(d[OFF + 15]),
          "+f"(d[OFF + 16]), "+f"(d[OFF + 17]), "+f"(d[OFF + 18]), "+f"(d[OFF + 19]), "+f"(d[OFF + 20]), "+f"(d[OFF + 21]), "+f"(d[OFF + 22]), "+f"(d[OFF + 23]),
          "+f"(d[OFF + 24]), "+f"(d[OFF + 25]), "+f"(d[OFF + 26]), "+f"(d[OFF + 27]), "+f"(d[OFF + 28]), "+f"(d[OFF + 29]), "+f"(d[OFF + 30]), "+f"(d[OFF + 31]),
          "+f"(d[OFF + 32]), "+f"(d[OFF + 33]), "+f"(d[OFF + 34]), "+f"(d[OFF + 35]), "+f"(d[OFF + 36]), "+f"(d[OFF + 37]), "+f"(d[OFF + 38]), "+f"(d[OFF + 39]),
          "+f"(d[OFF + 40]), "+f"(d[OFF + 41]), "+f"(d[OFF + 42]), "+f"(d[OFF + 43]), "+f"(d[OFF + 44]), "+f"(d[OFF + 45]), "+f"(d[OFF + 46]), "+f"(d[OFF + 47]),
          "+f"(d[OFF + 48]), "+f"(d[OFF + 49]), "+f"(d[OFF + 50]), "+f"(d[OFF + 51]), "+f"(d[OFF + 52]), "+f"(d[OFF + 53]), "+f"(d[OFF + 54]), "+f"(d[OFF + 55]),
          "+f"(d[OFF + 56]), "+f"(d[OFF + 57]), "+f"(d[OFF + 58]), "+f"(d[OFF + 59]), "+f"(d[OFF + 60]), "+f"(d[OFF + 61]), "+f"(d[OFF + 62]), "+f"(d[OFF + 63])
        : "r"(a0), "r"(a1), "r"(a2), "r"(a3), "l"(db), "r"(scale_d));
}


__global__ void __cluster_dims__(2, 1, 1) __launch_bounds__(kThreads, 1)
gqa_fwd_kernel(const __grid_constant__ CUtensorMap tmQ, const __grid_constant__ CUtensorMap tmK,
               const __grid_constant__ CUtensorMap tmV, const __grid_constant__ CUtensorMap tmO,
               const uint8_t* __restrict__ gq, const uint8_t* __restrict__ gk) {
    extern __shared__ __align__(1024) uint8_t smem_raw[];
    const uint32_t sb = smem_u32(smem_raw);
    const int wg = __shfl_sync(0xffffffffu, (int)(threadIdx.x >> 7), 0);
    const int warp_id = __shfl_sync(0xffffffffu, (int)(threadIdx.x >> 5), 0);
    const uint32_t rank = blockIdx.x & 1;
    int cl = blockIdx.x >> 1;
    if (cl >= 36) {
        const int i = cl - 36, round = i / 7, gpc = i - round * 7;
        cl = 2 * (18 + (round >> 1) * 7 + gpc) + (round & 1);
    } else if (cl >= 4) {
        const int i = cl - 4, round = i >> 3, gpc = i & 7;
        cl = 2 * (2 + (round >> 1) * 8 + gpc) + (round & 1);
    }
    const int slot = cl >> 1;
    const int qrow0 = cl * kSq + (int)rank * 128;
    constexpr int kTileRows = 64 * kSq;

    if (warp_id == 8) {
        const bool one = elect_one();
        if (one) {
            asm volatile("prefetch.tensormap [%0];" ::"l"(&tmQ) : "memory");
            asm volatile("prefetch.tensormap [%0];" ::"l"(&tmK) : "memory");
            asm volatile("prefetch.tensormap [%0];" ::"l"(&tmV) : "memory");
#pragma unroll
            for (int i = 0; i < 8; i++) mbar_init(sb + SM_BAR + i * 8, 1);
            asm volatile("fence.mbarrier_init.release.cluster;" ::: "memory");
        }
        __syncwarp();
        cluster_arrive_relaxed();
        if (one) {
            const uint32_t delay = (uint32_t)(slot & 3) * kStagger;
            uint32_t t0, t1;
            asm volatile("mov.u32 %0, %%clock;" : "=r"(t0));
            do {
                asm volatile("mov.u32 %0, %%clock;" : "=r"(t1));
            } while (t1 - t0 < delay);
#pragma unroll
            for (int c = 0; c < 4; c++) {
                mbar_expect_tx(sb + FULL_Q(0, c), 8192);
                tma_load_2d(sb + SM_Q + c * 8192, &tmQ, sb + FULL_Q(0, c), c * 64, qrow0);
            }
            l2_prefetch(gk + ((size_t)slot * kSk + ((cl & 1) * 2 + rank) * 32) * (kD * 2), 16384);
        }
        __syncwarp();
    } else if (warp_id == 9) {
        if (elect_one()) {
            asm volatile("prefetch.tensormap [%0];" ::"l"(&tmO) : "memory");
#pragma unroll
            for (int i = 8; i < kNumBars; i++) mbar_init(sb + SM_BAR + i * 8, bar_count(i));
            asm volatile("fence.mbarrier_init.release.cluster;" ::: "memory");
        }
        __syncwarp();
        cluster_arrive_relaxed();
    } else {
        cluster_arrive_relaxed();
    }
    cluster_wait();

    if (wg == 2) {
        asm volatile("setmaxnreg.dec.sync.aligned.u32 24;");
        if (warp_id == 8) {
            if (elect_one()) {
                uint32_t it = 0;
                for (int tile = 0; tile < kTiles; tile++) {
                    const int qrow = qrow0 + tile * kTileRows;
                    for (int j = 0; j < kIters; j++, it++) {
                        const int krow = (slot + tile * 32) * kSk + j * 128;
                        const uint32_t prev = (it - 1) & 1;
                        if (j == 0 && tile > 0) mbar_wait(sb + EMPTY_Q(0), 0);
#pragma unroll
                        for (int c = 0; c < 4; c++) {
                            if (j == 0 && tile > 0) {
                                mbar_expect_tx(sb + FULL_Q(0, c), 8192);
                                tma_load_2d(sb + SM_Q + c * 8192, &tmQ, sb + FULL_Q(0, c), c * 64, qrow);
                            }
                            if ((c & 1) == rank) {
                                if (it > 0) mbar_wait(sb + EMPTY_K(c), prev);
                                mbar_expect_tx(sb + FULL_K(c), 16384);
                                tma_load_2d_mc(sb + SM_K + c * 16384, &tmK, sb + FULL_K(c), c * 64, krow);
                            } else {
                                if (it > 0) mbar_wait(sb + FULL_K(c), prev);
                                mbar_expect_tx(sb + FULL_K(c), 16384);
                            }
                        }
                        if (j == 0) {
                            if (tile == 0) mbar_wait(sb + FULL_Q(0, 0), 0);
                            else mbar_wait(sb + EMPTY_Q(1), 0);
#pragma unroll
                            for (int c = 0; c < 4; c++) {
                                mbar_expect_tx(sb + FULL_Q(1, c), 8192);
                                tma_load_2d(sb + SM_Q + 32768 + c * 8192, &tmQ, sb + FULL_Q(1, c), c * 64, qrow + 64);
                            }
                        }
                        if (it == 0) mbar_wait(sb + FULL_K(3), 0);
#pragma unroll
                        for (int c = 0; c < 4; c++) {
                            if (c == 2 && it == 0) mbar_wait(sb + FULL_Q(1, 1), 0);
                            if ((c & 1) == rank) {
                                if (it > 0) mbar_wait(sb + EMPTY_V(c), prev);
                                mbar_expect_tx(sb + FULL_V(c), 16384);
                                tma_load_3d_mc(sb + SM_V + c * 16384, &tmV, sb + FULL_V(c), 0, krow + c * 32, 0);
                            } else {
                                if (it > 0) mbar_wait(sb + FULL_V(c), prev);
                                mbar_expect_tx(sb + FULL_V(c), 16384);
                            }
                        }
                    }
                }
                mbar_wait(sb + ALL_LOADED, 0);
            }
        } else if (warp_id == 11) {
            if (elect_one()) {
                const uint8_t* src = gq + (size_t)(qrow0 + kTileRows) * (kD * 2);
                mbar_expect_tx(sb + WARM_DONE, 65536);
#pragma unroll 1
                for (int c = 0; c < 8; c++) mbar_wait(sb + FULL_K(0) + c * 8, 0);
#pragma unroll 1
                for (int e = 0; e < kWarmEvents; e++) {
                    mbar_wait(sb + FULL_K(0) + ((e + kWarmFirst) & 7) * 8, ((e + kWarmFirst) >> 3) & 1);
                    const int p0 = (e * kWarmStep) >> 4, p1 = min(32, ((e + 1) * kWarmStep) >> 4);
                    for (int p = p0; p < p1; p++)
                        asm volatile("cp.async.bulk.shared::cluster.global.mbarrier::complete_tx::bytes [%0], [%1], 2048, [%2];"
                                     ::"r"(sb + SM_JUNK), "l"(src + p * 2048), "r"(sb + WARM_DONE) : "memory");
                }
                mbar_wait(sb + WARM_DONE, 0);
            }
        } else if (warp_id == 9) {
            const bool one = elect_one();
#pragma unroll 1
            for (int h = 0; h < 2; h++) {
                named_sync(BAR_OREADY0 + 2 + h, 160);
                if (one) {
                    tma_store_3d(&tmO, sb + SM_V + 32768 + h * 16384, 0, qrow0 + 64, 2 * h);
                    tma_store_3d(&tmO, sb + SM_V + 32768 + h * 16384 + 8192, 0, qrow0 + 64, 2 * h + 1);
                    asm volatile("cp.async.bulk.commit_group;" ::: "memory");
                    asm volatile("cp.async.bulk.wait_group.read 0;" ::: "memory");
                    mbar_arrive_cluster(mapa(sb, h) + EMPTY_V(2) + h * 8);
                }
                __syncwarp();
            }
#pragma unroll 1
            for (int h = 0; h < 2; h++) {
                named_sync(BAR_OREADY0 + h, 160);
                if (one) {
                    mbar_wait(sb + (h == 0 ? FULL_K(3) : FULL_V(3)), 1);
                    tma_store_3d(&tmO, sb + SM_O + h * 16384, 0, qrow0, 2 * h);
                    tma_store_3d(&tmO, sb + SM_O + h * 16384 + 8192, 0, qrow0, 2 * h + 1);
                    asm volatile("cp.async.bulk.commit_group;" ::: "memory");
                }
                __syncwarp();
            }
#pragma unroll 1
            for (int u = 0; u < 8; u++) {
                named_sync(BAR_OLAST0 + u, 160);
                if (one) {
                    tma_store_3d(&tmO, sb + SM_Q + u * 8192, 0, qrow0 + kTileRows + (u >> 2) * 64, u & 3);
                    asm volatile("cp.async.bulk.commit_group;" ::: "memory");
                }
                __syncwarp();
            }
            if (one) asm volatile("cp.async.bulk.wait_group.read 0;" ::: "memory");
        }
    } else {
        asm volatile("setmaxnreg.inc.sync.aligned.u32 240;");
        const int lane = threadIdx.x & 31;
        const int warp = (threadIdx.x >> 5) & 3;
        const bool leader = (threadIdx.x & 127) == 0;
        const uint32_t dq = desc_lo(sb + SM_Q + wg * 32768, 16);
        const uint32_t dk = desc_lo(sb + SM_K, 16);
        const uint32_t dv = desc_lo(sb + SM_V, 4096);
        const uint32_t peer0 = mapa(sb, 0), peer1 = mapa(sb, 1);
        const int my_order = BAR_ORDER0 + wg;
        constexpr float kScaleLog2e = 0.0625f * 1.4426950408889634f;
        constexpr float kRescaleLog2 = 8.0f;

        float o[128];
#pragma unroll
        for (int i = 0; i < 128; i++) o[i] = 0.f;
        float m0 = -INFINITY, m1 = -INFINITY, l0 = 0.f, l1 = 0.f;
        int thr0 = INT_MIN, thr1 = INT_MIN;
        float inv0 = 0.f, inv1 = 0.f;

        auto finish_row_sums = [&]() {
            l0 += __shfl_xor_sync(0xffffffffu, l0, 1);
            l1 += __shfl_xor_sync(0xffffffffu, l1, 1);
            l0 += __shfl_xor_sync(0xffffffffu, l0, 2);
            l1 += __shfl_xor_sync(0xffffffffu, l1, 2);
            inv0 = rcp_approx(l0);
            inv1 = rcp_approx(l1);
        };
        auto stage_block = [&](auto blk, uint32_t stage) {
            constexpr int b = decltype(blk)::value;
            const int r = lane & 7, mi = lane >> 3;
            const uint32_t base = stage + b * 8192 + (warp * 16 + r + 8 * (mi & 1)) * 128 + (((mi >> 1) ^ r) << 4);
#pragma unroll
            for (int i = 4 * b; i < 4 * b + 4; i++) {
                const uint32_t r0 = pack_bf16(o[8 * i + 0] * inv0, o[8 * i + 1] * inv0);
                const uint32_t r1 = pack_bf16(o[8 * i + 2] * inv1, o[8 * i + 3] * inv1);
                const uint32_t r2 = pack_bf16(o[8 * i + 4] * inv0, o[8 * i + 5] * inv0);
                const uint32_t r3 = pack_bf16(o[8 * i + 6] * inv1, o[8 * i + 7] * inv1);
                asm volatile("stmatrix.sync.aligned.m8n8.x4.shared.b16 [%0], {%1, %2, %3, %4};"
                             ::"r"(base ^ ((i & 3) << 5)), "r"(r0), "r"(r1), "r"(r2), "r"(r3) : "memory");
            }
        };
        auto hand_over = [&](int barrier) {
            asm volatile("fence.proxy.async.shared::cta;" ::: "memory");
            named_arrive(barrier, 160);
        };

        auto iteration = [&](auto last, const uint32_t it) {
            constexpr bool kLast = decltype(last)::value != 0;
            const uint32_t j = kLast ? kIters - 1 : (it & (kIters - 1));
            const uint32_t par = it & 1;
            const bool release = leader && !kLast;
            float s[64];
            named_sync(my_order, 256);
#pragma unroll
            for (int c = 0; c < 4; c++) {
                if (!kLast && j == 0) mbar_wait(sb + FULL_Q(0, c) + wg * 32, it >> 2);
                mbar_wait(sb + FULL_K(c), par);
                if (c == 0) wg_fence();
#pragma unroll
                for (int kk = 0; kk < 4; kk++) {
                    const uint64_t da = desc_at(dq, c * 8192 + kk * 32);
                    const uint64_t db = desc_at(dk, c * 16384 + kk * 32);
                    if (c == 0 && kk == 0) wgmma_qk_first(s, da, db);
                    else wgmma_qk(s, da, db);
                }
                wg_commit();
            }
            if (wg == 0) named_arrive(BAR_ORDER0 + 1, 256);
            else if (!kLast && j == 0) named_arrive(BAR_FIRST_PV, 256);
            if (!kLast) {
                wg_wait<3>();
                if (release) mbar_arrive_cluster(peer0 + EMPTY_K(0));
                wg_wait<2>();
                if (release) mbar_arrive_cluster(peer1 + EMPTY_K(1));
                wg_wait<1>();
                if (release) mbar_arrive_cluster(peer0 + EMPTY_K(2));
            }
            wg_wait<0>();
            fence_regs(s);
            if (!kLast) {
                if (release) mbar_arrive_cluster(peer1 + EMPTY_K(3));
                if (leader && it == kIters - 1) mbar_arrive(sb + EMPTY_Q(0) + wg * 8);
            }

            int ia[3], ib[3];
#pragma unroll
            for (int q = 0; q < 3; q++) {
                const int i0 = q * 20;
                ia[q] = __vimax3_s32(__float_as_int(s[i0]), __float_as_int(s[i0 + 1]), __float_as_int(s[i0 + 4]));
                ib[q] = __vimax3_s32(__float_as_int(s[i0 + 2]), __float_as_int(s[i0 + 3]), __float_as_int(s[i0 + 6]));
                ia[q] = __vimax3_s32(ia[q], __float_as_int(s[i0 + 5]), __float_as_int(s[i0 + 8]));
                ib[q] = __vimax3_s32(ib[q], __float_as_int(s[i0 + 7]), __float_as_int(s[i0 + 10]));
                ia[q] = __vimax3_s32(ia[q], __float_as_int(s[i0 + 9]), __float_as_int(s[i0 + 12]));
                ib[q] = __vimax3_s32(ib[q], __float_as_int(s[i0 + 11]), __float_as_int(s[i0 + 14]));
                ia[q] = __vimax3_s32(ia[q], __float_as_int(s[i0 + 13]), __float_as_int(s[i0 + 16]));
                ib[q] = __vimax3_s32(ib[q], __float_as_int(s[i0 + 15]), __float_as_int(s[i0 + 18]));
                ia[q] = max(ia[q], __float_as_int(s[i0 + 17]));
                ib[q] = max(ib[q], __float_as_int(s[i0 + 19]));
            }
            int im0 = __vimax3_s32(ia[0], ia[1], ia[2]), im1 = __vimax3_s32(ib[0], ib[1], ib[2]);
            im0 = __vimax3_s32(im0, __float_as_int(s[60]), __float_as_int(s[61]));
            im1 = __vimax3_s32(im1, __float_as_int(s[62]), __float_as_int(s[63]));
            if (__any_sync(0xffffffffu, im0 >= thr0 || im1 >= thr1)) {
                im0 = max(im0, __shfl_xor_sync(0xffffffffu, im0, 1));
                im1 = max(im1, __shfl_xor_sync(0xffffffffu, im1, 1));
                im0 = max(im0, __shfl_xor_sync(0xffffffffu, im0, 2));
                im1 = max(im1, __shfl_xor_sync(0xffffffffu, im1, 2));
                float mx0 = __int_as_float(im0), mx1 = __int_as_float(im1);
                if (__any_sync(0xffffffffu, (im0 | im1) < 0)) {
                    mx0 = fmaxf(s[0], s[1]);
                    mx1 = fmaxf(s[2], s[3]);
#pragma unroll
                    for (int i = 1; i < 16; i++) {
                        mx0 = fmaxf(mx0, fmaxf(s[4 * i], s[4 * i + 1]));
                        mx1 = fmaxf(mx1, fmaxf(s[4 * i + 2], s[4 * i + 3]));
                    }
                    mx0 = fmaxf(mx0, __shfl_xor_sync(0xffffffffu, mx0, 1));
                    mx1 = fmaxf(mx1, __shfl_xor_sync(0xffffffffu, mx1, 1));
                    mx0 = fmaxf(mx0, __shfl_xor_sync(0xffffffffu, mx0, 2));
                    mx1 = fmaxf(mx1, __shfl_xor_sync(0xffffffffu, mx1, 2));
                }
                const float mn0 = fmaxf(m0, mx0 * kScaleLog2e), mn1 = fmaxf(m1, mx1 * kScaleLog2e);
                if (j > 0) {
                    const float al0 = ex2(m0 - mn0), al1 = ex2(m1 - mn1);
                    l0 *= al0;
                    l1 *= al1;
#pragma unroll
                    for (int i = 0; i < 128; i++) o[i] *= (i & 2) ? al1 : al0;
                }
                m0 = mn0;
                m1 = mn1;
                const float lim0 = (mn0 + kRescaleLog2) * (1.0f / kScaleLog2e), lim1 = (mn1 + kRescaleLog2) * (1.0f / kScaleLog2e);
                thr0 = lim0 >= 0.f ? __float_as_int(lim0) : INT_MIN;
                thr1 = lim1 >= 0.f ? __float_as_int(lim1) : INT_MIN;
            }

            uint32_t p[32];
            auto exp_chunk = [&](int c) {
#pragma unroll
                for (int kk = 2 * c; kk < 2 * c + 2; kk++) {
                    float e[8];
#pragma unroll
                    for (int i = 0; i < 8; i++) e[i] = ex2(fmaf(s[8 * kk + i], kScaleLog2e, (i & 2) ? -m1 : -m0));
                    l0 += (e[0] + e[1]) + (e[4] + e[5]);
                    l1 += (e[2] + e[3]) + (e[6] + e[7]);
                    p[4 * kk + 0] = pack_bf16(e[0], e[1]);
                    p[4 * kk + 1] = pack_bf16(e[2], e[3]);
                    p[4 * kk + 2] = pack_bf16(e[4], e[5]);
                    p[4 * kk + 3] = pack_bf16(e[6], e[7]);
                }
            };
            exp_chunk(0);
#pragma unroll
            for (int c = 0; c < 4; c++) {
                if (c < 3) exp_chunk(c + 1);
                if (!kLast && c == 0 && wg == 0 && j == 0) named_sync(BAR_FIRST_PV, 256);
                mbar_wait(sb + FULL_V(c), par);
                wg_fence();
#pragma unroll
                for (int kk = 0; kk < 2; kk++) {
                    const int k8 = c * 2 + kk;
                    const uint64_t db = desc_at(dv, c * 16384 + kk * 2048);
                    wgmma_pv_half<0>(o, p[4 * k8], p[4 * k8 + 1], p[4 * k8 + 2], p[4 * k8 + 3], db, (k8 == 0) ? j : 1);
                    if (!kLast) wgmma_pv_half<64>(o, p[4 * k8], p[4 * k8 + 1], p[4 * k8 + 2], p[4 * k8 + 3], db + (8192 >> 4), (k8 == 0) ? j : 1);
                }
                if (!kLast || c == 3) wg_commit();
            }
            if (!kLast) {
                if (wg == 1) named_arrive(BAR_ORDER0, 256);
                const bool release_hi = release && !(wg == 1 && j == kIters - 1);
                wg_wait<3>();
                if (release) mbar_arrive_cluster(peer0 + EMPTY_V(0));
                wg_wait<2>();
                if (release) mbar_arrive_cluster(peer1 + EMPTY_V(1));
                wg_wait<1>();
                if (release_hi) mbar_arrive_cluster(peer0 + EMPTY_V(2));
                wg_wait<0>();
                fence_regs(o);
                if (release_hi) mbar_arrive_cluster(peer1 + EMPTY_V(3));
                if (wg == 0 && it == kIters - 1) named_arrive(BAR_VDONE, 256);
            } else {
#pragma unroll
                for (int k8 = 0; k8 < 8; k8++) {
                    const uint64_t db = desc_at(dv, (k8 >> 1) * 16384 + (k8 & 1) * 2048 + 8192);
                    wgmma_pv_half<64>(o, p[4 * k8], p[4 * k8 + 1], p[4 * k8 + 2], p[4 * k8 + 3], db, 1);
                }
                wg_commit();
                if (leader) {
                    mbar_arrive_cluster(peer0 + ALL_LOADED);
                    mbar_arrive_cluster(peer1 + ALL_LOADED);
                }
                const uint32_t stage = sb + SM_Q + wg * 32768;
                finish_row_sums();
                wg_wait<1>();
                fence_regs_range<0>(o);
                stage_block(IntC<0>{}, stage);
                hand_over(BAR_OLAST0 + wg * 4 + 0);
                stage_block(IntC<1>{}, stage);
                hand_over(BAR_OLAST0 + wg * 4 + 1);
                wg_wait<0>();
                fence_regs_range<64>(o);
                stage_block(IntC<2>{}, stage);
                hand_over(BAR_OLAST0 + wg * 4 + 2);
                stage_block(IntC<3>{}, stage);
                hand_over(BAR_OLAST0 + wg * 4 + 3);
            }
        };

        if (wg == 1) named_arrive(BAR_ORDER0, 256);
#pragma unroll 1
        for (uint32_t it = 0; it < kTiles * kIters - 1; it++) {
            iteration(IntC<0>{}, it);
            if (it == kIters - 1) {
                finish_row_sums();
                if (wg == 1) named_sync(BAR_VDONE, 256);
                const uint32_t stage = sb + (wg == 0 ? SM_O : SM_V + 32768);
                stage_block(IntC<0>{}, stage);
                stage_block(IntC<1>{}, stage);
                hand_over(BAR_OREADY0 + wg * 2);
                stage_block(IntC<2>{}, stage);
                stage_block(IntC<3>{}, stage);
                hand_over(BAR_OREADY0 + wg * 2 + 1);
                m0 = m1 = -INFINITY;
                l0 = l1 = 0.f;
                thr0 = thr1 = INT_MIN;
            }
        }
        iteration(IntC<1>{}, kTiles * kIters - 1);
    }
}

typedef CUresult (*EncodeTiledFn)(CUtensorMap*, CUtensorMapDataType, cuuint32_t, void*, const cuuint64_t*,
                                  const cuuint64_t*, const cuuint32_t*, const cuuint32_t*, CUtensorMapInterleave,
                                  CUtensorMapSwizzle, CUtensorMapL2promotion, CUtensorMapFloatOOBfill);

void encode_2d(EncodeTiledFn fn, CUtensorMap* m, void* ptr, uint64_t rows, uint32_t box_rows) {
    cuuint64_t dims[2] = {(cuuint64_t)kD, rows};
    cuuint64_t strides[1] = {(cuuint64_t)kD * 2};
    cuuint32_t box[2] = {64, box_rows};
    cuuint32_t es[2] = {1, 1};
    fn(m, CU_TENSOR_MAP_DATA_TYPE_BFLOAT16, 2, ptr, dims, strides, box, es, CU_TENSOR_MAP_INTERLEAVE_NONE,
       CU_TENSOR_MAP_SWIZZLE_128B, CU_TENSOR_MAP_L2_PROMOTION_L2_128B, CU_TENSOR_MAP_FLOAT_OOB_FILL_NONE);
}
void encode_3d(EncodeTiledFn fn, CUtensorMap* m, void* ptr, uint64_t rows, uint32_t box_rows, uint32_t box_blocks) {
    cuuint64_t dims[3] = {64, rows, 4};
    cuuint64_t strides[2] = {(cuuint64_t)kD * 2, 128};
    cuuint32_t box[3] = {64, box_rows, box_blocks};
    cuuint32_t es[3] = {1, 1, 1};
    fn(m, CU_TENSOR_MAP_DATA_TYPE_BFLOAT16, 3, ptr, dims, strides, box, es, CU_TENSOR_MAP_INTERLEAVE_NONE,
       CU_TENSOR_MAP_SWIZZLE_128B, CU_TENSOR_MAP_L2_PROMOTION_L2_128B, CU_TENSOR_MAP_FLOAT_OOB_FILL_NONE);
}

}

extern "C" void kernel_launch(void* const* d_in, const int* in_sizes, int n_in, void* d_out, int out_size) {
    static EncodeTiledFn encode = nullptr;
    if (!encode) {
        void* fn = nullptr;
        cudaDriverEntryPointQueryResult qr;
        cudaGetDriverEntryPoint("cuTensorMapEncodeTiled", &fn, cudaEnableDefault, &qr);
        encode = (EncodeTiledFn)fn;
        cudaFuncSetAttribute(gqa_fwd_kernel, cudaFuncAttributeMaxDynamicSharedMemorySize, kSmemBytes);
    }
    CUtensorMap tmQ, tmK, tmV, tmO;
    encode_2d(encode, &tmQ, d_in[0], kQRows, 64);
    encode_2d(encode, &tmK, d_in[1], kKvRows, 128);
    encode_3d(encode, &tmV, d_in[2], kKvRows, 32, 4);
    encode_3d(encode, &tmO, d_out, kQRows, 64, 1);
    gqa_fwd_kernel<<<kCtas, kThreads, kSmemBytes>>>(tmQ, tmK, tmV, tmO, (const uint8_t*)d_in[0], (const uint8_t*)d_in[1]);
}
```
